```python
import torch

def _softmax(x, axis=-1):
    return torch.softmax(x, dim=axis)
def _gelu(x):
    return torch.nn.functional.gelu(x, approximate="tanh")
def _silu(x):
    return torch.nn.functional.silu(x)
def _sigmoid(x):
    return torch.sigmoid(x)
def _layernorm(x, axis=-1, eps=1e-5):
    m = x.mean(dim=axis, keepdim=True)
    v = x.var(dim=axis, keepdim=True, unbiased=False)
    return (x - m) / torch.sqrt(v + eps)
def _scatter_add(tgt, idx, src, axis=0):
    return tgt.clone().index_add_(axis, idx, src)
def _segment_sum(src, seg, n):
    out = torch.zeros((n,) + src.shape[1:], dtype=src.dtype)
    return out.index_add_(0, seg, src)
def _pad(x, pw):
    flat = tuple(v for pair in reversed(pw) for v in pair)
    return torch.nn.functional.pad(x, flat)

kernel_name = 'standalone__deep_cross_wide_deep__recsys'

def setup_inputs():

    _w = (lambda a: (lambda t: t.to(torch.bfloat16) if t.is_floating_point() else t)(torch.as_tensor(a)))
    B, F, D = 16384, 100, 32
    V, Nd = min(1000, 100000), 13
    Din = F * D
    H = 4 * D
    return {
        "idx": _w((lambda lo, hi, *s: torch.randint(lo, hi, s))(0, V, B, F).to(torch.int64)),
        "table": _w((lambda *s: torch.randn(*s, dtype=torch.bfloat16) * 1.6)(V, D) * 0.05),
        "x_wide": _w((lambda *s: torch.randn(*s, dtype=torch.bfloat16) * 1.6)(B, Nd)),
        "w_wide": _w((lambda *s: torch.randn(*s, dtype=torch.bfloat16) * 1.6)(Nd) * 0.05),
        "b_wide": _w((lambda *s: torch.randn(*s, dtype=torch.bfloat16) * 1.6)(1) * 0.01),
        "W1": _w((lambda *s: torch.randn(*s, dtype=torch.bfloat16) * 1.6)(Din, H) * (2.0 / Din) ** 0.5),
        "b1": _w((lambda *s: torch.randn(*s, dtype=torch.bfloat16) * 1.6)(H) * 0.01),
        "W2": _w((lambda *s: torch.randn(*s, dtype=torch.bfloat16) * 1.6)(H) * (1.0 / H) ** 0.5),
        "b2": _w((lambda *s: torch.randn(*s, dtype=torch.bfloat16) * 1.6)(1) * 0.01),
    }

def reference(idx, table, x_wide, w_wide, b_wide, W1, b1, W2, b2):
    emb = table[idx]
    deep_in = emb.reshape(emb.shape[0], -1)
    h = deep_in @ W1 + b1
    h = h * (lambda x, dt: x.to(dt))(h > 0, h.dtype)
    deep_logit = h @ W2 + b2
    wide_logit = x_wide @ w_wide + b_wide
    return _sigmoid(wide_logit + deep_logit)
```

```cpp
#include <cuda_runtime.h>
#include <cuda_bf16.h>
#include <cuda.h>
#include <stdint.h>

namespace {

constexpr int kB = 16384, kF = 100, kV = 1000, kNd = 13, kH = 128;
constexpr int kRows = 128;
constexpr int kGrid = kB / kRows;
constexpr int kStageBytes = 16384;
constexpr int kNumStages = 6;
constexpr int kNumK = kF / 2;
constexpr int kThreads = 320;

constexpr int kEarlyChunks = 5;
constexpr int kOffW = 0;
constexpr int kOffTab = kNumStages * kStageBytes;
constexpr int kOffIdx = kOffTab + kV * 64;
constexpr int kOffEarly = kOffIdx + kRows * kF * 4;
constexpr int kOffB1 = kOffEarly + kRows * kEarlyChunks * 16;
constexpr int kOffW2 = kOffB1 + 256;
constexpr int kOffWide = kOffW2 + 256;
constexpr int kOffBar = kOffWide + 512 + 16;
constexpr int kBarFull = kOffBar, kBarEmpty = kOffBar + 64, kBarTab = kOffBar + 128, kBarIdx = kOffBar + 136,
              kBarMisc = kOffBar + 144;
constexpr int kSmemBytes = kOffBar + 160;

#define STAMP(i)

__device__ __forceinline__ uint32_t smem_u32(const void* p) { return (uint32_t)__cvta_generic_to_shared(p); }
__device__ __forceinline__ void mbar_init(uint32_t bar, uint32_t cnt) {
    asm volatile("mbarrier.init.shared::cta.b64 [%0], %1;" ::"r"(bar), "r"(cnt) : "memory");
}
__device__ __forceinline__ void mbar_wait(uint32_t bar, uint32_t parity) {
    asm volatile(
        "{\n.reg .pred p;\n.reg .u32 c;\nmov.u32 c, 0;\n"
        "LAB_WAIT:\n"
        "mbarrier.try_wait.parity.shared::cta.b64 p, [%0], %1;\n"
        "@p bra.uni LAB_DONE;\n"
        "add.u32 c, c, 1;\n"
        "setp.gt.u32 p, c, 4000000;\n"
        "@p trap;\n"
        "bra.uni LAB_WAIT;\n"
        "LAB_DONE:\n}" ::"r"(bar), "r"(parity) : "memory");
}
__device__ __forceinline__ void mbar_arrive_if(uint32_t bar, uint32_t pred) {
    asm volatile("{\n.reg .pred p;\nsetp.ne.u32 p, %1, 0;\n@p mbarrier.arrive.shared::cta.b64 _, [%0];\n}" ::"r"(bar),
                 "r"(pred) : "memory");
}
__device__ __forceinline__ void mbar_expect_tx(uint32_t bar, uint32_t bytes) {
    asm volatile("mbarrier.arrive.expect_tx.shared::cta.b64 _, [%0], %1;" ::"r"(bar), "r"(bytes) : "memory");
}
__device__ __forceinline__ void bulk_g2s(uint32_t dst, const void* src, uint32_t bytes, uint32_t bar) {
    asm volatile("cp.async.bulk.shared::cluster.global.mbarrier::complete_tx::bytes [%0], [%1], %2, [%3];" ::"r"(dst),
                 "l"(src), "r"(bytes), "r"(bar) : "memory");
}
__device__ __forceinline__ void bulk_prefetch_l2(const void* src, uint32_t bytes) {
    asm volatile("cp.async.bulk.prefetch.L2.global [%0], %1;" ::"l"(src), "r"(bytes) : "memory");
}
__device__ __forceinline__ void tma_w1(uint32_t dst, const CUtensorMap* map, int qf, uint32_t bar) {
    asm volatile(
        "cp.async.bulk.tensor.5d.shared::cluster.global.mbarrier::complete_tx::bytes [%0], [%1, {%3, %3, %4, %3, %3}], [%2];" ::"r"(dst),
        "l"(map), "r"(bar), "r"(0), "r"(qf) : "memory");
}
__device__ __forceinline__ uint4 lds128(uint32_t addr) {
    uint4 v;
    asm volatile("ld.shared.v4.u32 {%0,%1,%2,%3}, [%4];" : "=r"(v.x), "=r"(v.y), "=r"(v.z), "=r"(v.w) : "r"(addr));
    return v;
}
__device__ __forceinline__ void wgmma_fence() { asm volatile("wgmma.fence.sync.aligned;" ::: "memory"); }
__device__ __forceinline__ void wgmma_commit() { asm volatile("wgmma.commit_group.sync.aligned;" ::: "memory"); }
__device__ __forceinline__ void wgmma_wait0() { asm volatile("wgmma.wait_group.sync.aligned 0;" ::: "memory"); }

constexpr uint32_t kDescHi = (1u << 30) | (4096 >> 4);
constexpr uint32_t kDescLoLbo = (8192 >> 4) << 16;

__device__ __forceinline__ void wgmma_rs(float (&d)[64], uint32_t a0, uint32_t a1, uint32_t a2, uint32_t a3,
                                         uint32_t dlo) {
    asm volatile(
        "{\n.reg .pred p;\n.reg .b64 db;\nsetp.ne.b32 p, 1, 0;\nmov.b64 db, {%68, %69};\n"
        "wgmma.mma_async.sync.aligned.m64n128k16.f32.bf16.bf16 "
        "{%0,%1,%2,%3,%4,%5,%6,%7,%8,%9,%10,%11,%12,%13,%14,%15,"
        "%16,%17,%18,%19,%20,%21,%22,%23,%24,%25,%26,%27,%28,%29,%30,%31,"
        "%32,%33,%34,%35,%36,%37,%38,%39,%40,%41,%42,%43,%44,%45,%46,%47,"
        "%48,%49,%50,%51,%52,%53,%54,%55,%56,%57,%58,%59,%60,%61,%62,%63},"
        "{%64,%65,%66,%67}, db, p, 1, 1, 1;\n}"
        : "+f"(d[0]), "+f"(d[1]), "+f"(d[2]), "+f"(d[3]), "+f"(d[4]), "+f"(d[5]), "+f"(d[6]), "+f"(d[7]),
          "+f"(d[8]), "+f"(d[9]), "+f"(d[10]), "+f"(d[11]), "+f"(d[12]), "+f"(d[13]), "+f"(d[14]), "+f"(d[15]),
          "+f"(d[16]), "+f"(d[17]), "+f"(d[18]), "+f"(d[19]), "+f"(d[20]), "+f"(d[21]), "+f"(d[22]), "+f"(d[23]),
          "+f"(d[24]), "+f"(d[25]), "+f"(d[26]), "+f"(d[27]), "+f"(d[28]), "+f"(d[29]), "+f"(d[30]), "+f"(d[31]),
          "+f"(d[32]), "+f"(d[33]), "+f"(d[34]), "+f"(d[35]), "+f"(d[36]), "+f"(d[37]), "+f"(d[38]), "+f"(d[39]),
          "+f"(d[40]), "+f"(d[41]), "+f"(d[42]), "+f"(d[43]), "+f"(d[44]), "+f"(d[45]), "+f"(d[46]), "+f"(d[47]),
          "+f"(d[48]), "+f"(d[49]), "+f"(d[50]), "+f"(d[51]), "+f"(d[52]), "+f"(d[53]), "+f"(d[54]), "+f"(d[55]),
          "+f"(d[56]), "+f"(d[57]), "+f"(d[58]), "+f"(d[59]), "+f"(d[60]), "+f"(d[61]), "+f"(d[62]), "+f"(d[63])
        : "r"(a0), "r"(a1), "r"(a2), "r"(a3), "r"(dlo), "n"(kDescHi));
}
__device__ __forceinline__ void mma_stage(float (&acc)[64], const uint4 (&A)[4], uint32_t dlo) {
    wgmma_fence();
    wgmma_rs(acc, A[0].x, A[1].x, A[0].z, A[1].z, dlo);
    wgmma_rs(acc, A[0].y, A[1].y, A[0].w, A[1].w, dlo + (2048 >> 4));
    wgmma_rs(acc, A[2].x, A[3].x, A[2].z, A[3].z, dlo + (1024 >> 4));
    wgmma_rs(acc, A[2].y, A[3].y, A[2].w, A[3].w, dlo + (3072 >> 4));
    wgmma_commit();
}
__device__ __forceinline__ void mma16816(float (&c)[4], uint32_t a0, uint32_t a1, uint32_t a2, uint32_t a3, uint32_t b0,
                                         uint32_t b1) {
    asm volatile("mma.sync.aligned.m16n8k16.row.col.f32.bf16.bf16.f32 {%0,%1,%2,%3}, {%4,%5,%6,%7}, {%8,%9}, {%0,%1,%2,%3};"
                 : "+f"(c[0]), "+f"(c[1]), "+f"(c[2]), "+f"(c[3])
                 : "r"(a0), "r"(a1), "r"(a2), "r"(a3), "r"(b0), "r"(b1));
}
__device__ __forceinline__ uint32_t bias_relu(float lo, float hi, uint32_t bias) {
    uint32_t h, r;
    asm("cvt.rn.bf16x2.f32 %0, %1, %2;" : "=r"(h) : "f"(hi), "f"(lo));
    asm("fma.rn.relu.bf16x2 %0, %1, %2, %3;" : "=r"(r) : "r"(h), "r"(0x3F803F80u), "r"(bias));
    return r;
}
__device__ __forceinline__ float bf16r(float x) { return __bfloat162float(__float2bfloat16_rn(x)); }
__device__ __forceinline__ float bf16lo(uint32_t w) { return __uint_as_float(w << 16); }
__device__ __forceinline__ float bf16hi(uint32_t w) { return __uint_as_float(w & 0xFFFF0000u); }

__global__ void __launch_bounds__(kThreads, 1)
wide_deep_kernel(const __grid_constant__ CUtensorMap mapW1, const int* __restrict__ idx,
                 const __nv_bfloat16* __restrict__ table, const __nv_bfloat16* __restrict__ x_wide,
                 const __nv_bfloat16* __restrict__ w_wide, const __nv_bfloat16* __restrict__ b_wide,
                 const __nv_bfloat16* __restrict__ W1, const __nv_bfloat16* __restrict__ b1,
                 const __nv_bfloat16* __restrict__ W2, const __nv_bfloat16* __restrict__ b2,
                 __nv_bfloat16* __restrict__ out) {
    extern __shared__ __align__(1024) uint8_t smem[];
    const uint32_t sb = smem_u32(smem);
    const int tid = threadIdx.x, warp = tid >> 5, lane = tid & 31;
    const int cta = blockIdx.x;

    if (warp == 8) {
        if (lane == 0) {
#pragma unroll
            for (int s = 0; s < kNumStages; s++) {
                mbar_init(sb + kBarFull + s * 8, 1);
                mbar_init(sb + kBarEmpty + s * 8, 2);
            }
            mbar_init(sb + kBarTab, 1);
            mbar_init(sb + kBarIdx, 1);
            mbar_init(sb + kBarMisc, 32);
            asm volatile("fence.proxy.async.shared::cta;" ::: "memory");
            mbar_expect_tx(sb + kBarTab, kV * 64);
            mbar_expect_tx(sb + kBarFull, kStageBytes);
            tma_w1(sb + kOffW, &mapW1, 0, sb + kBarFull);
#pragma unroll
            for (int i = 0; i < 8; i++) {
                const uint32_t o = ((cta + i) & 7) * 8000;
                bulk_g2s(sb + kOffTab + o, (const uint8_t*)table + o, 8000, sb + kBarTab);
            }
        }
        __syncwarp();
        asm volatile("bar.arrive 1, %0;" ::"n"(kThreads) : "memory");
        if (lane == 0) {
            bulk_prefetch_l2((const uint8_t*)W1 + cta * 6400, 6400);
#pragma unroll
            for (int s = 1; s < kNumStages; s++) {
                mbar_expect_tx(sb + kBarFull + s * 8, kStageBytes);
                tma_w1(sb + kOffW + s * kStageBytes, &mapW1, s * 8, sb + kBarFull + s * 8);
                if (s == 2) {
                    mbar_expect_tx(sb + kBarIdx, kRows * kF * 4);
                    bulk_g2s(sb + kOffIdx, idx + (size_t)cta * (kRows * kF), kRows * kF * 4, sb + kBarIdx);
                }
            }
            int st = 0;
            uint32_t ph = 0;
#pragma unroll 1
            for (int k = kNumStages; k < kNumK; k++) {
                mbar_wait(sb + kBarEmpty + st * 8, ph);
                mbar_expect_tx(sb + kBarFull + st * 8, kStageBytes);
                tma_w1(sb + kOffW + st * kStageBytes, &mapW1, k * 8, sb + kBarFull + st * 8);
                if (++st == kNumStages) { st = 0; ph ^= 1; }
            }
        }
    } else if (warp == 9) {
        uint2 xw[13];
        const uint2* xp = (const uint2*)((const uint8_t*)x_wide + (size_t)cta * (kRows * kNd * 2) + lane * (4 * kNd * 2));
#pragma unroll
        for (int i = 0; i < 13; i++) xw[i] = __ldg(xp + i);
        float ww[kNd];
#pragma unroll
        for (int i = 0; i < kNd; i++) ww[i] = __bfloat162float(w_wide[i]);
        const float bw = __bfloat162float(b_wide[0]);
        const float bb2 = __bfloat162float(b2[0]);
        const uint2 vb1 = __ldg((const uint2*)b1 + lane), vw2 = __ldg((const uint2*)W2 + lane);
        asm volatile("bar.sync 1, %0;" ::"n"(kThreads) : "memory");
        {
            const int t0 = 2 * lane, t1 = 2 * lane + 1;
            uint32_t* sb1 = (uint32_t*)(smem + kOffB1);
            uint32_t* sw2 = (uint32_t*)(smem + kOffW2);
            sb1[(t0 & 3) * 16 + (t0 >> 2)] = vb1.x;
            sb1[(t1 & 3) * 16 + (t1 >> 2)] = vb1.y;
            sw2[(t0 & 3) * 16 + (t0 >> 2)] = vw2.x;
            sw2[(t1 & 3) * 16 + (t1 >> 2)] = vw2.y;
        }
        float wl[4] = {0.f, 0.f, 0.f, 0.f};
#pragma unroll
        for (int e = 0; e < 52; e++) {
            const uint32_t w = (e & 2) ? xw[e >> 2].y : xw[e >> 2].x;
            const float x = (e & 1) ? bf16hi(w) : bf16lo(w);
            wl[e / 13] = fmaf(x, ww[e % 13], wl[e / 13]);
        }
        float4 o;
        o.x = bf16r(bf16r(wl[0]) + bw);
        o.y = bf16r(bf16r(wl[1]) + bw);
        o.z = bf16r(bf16r(wl[2]) + bw);
        o.w = bf16r(bf16r(wl[3]) + bw);
        *(float4*)(smem + kOffWide + lane * 16) = o;
        if (lane == 0) *(float*)(smem + kOffWide + 512) = bb2;
        mbar_arrive_if(sb + kBarMisc, 1);
    } else {
        STAMP(0 + (tid >> 7) * 8);
        const int g = lane >> 2, q = lane & 3;
        const int r0 = warp * 16 + g;
        const uint8_t* widx = (const uint8_t*)(idx + ((size_t)cta * kRows + warp * 16) * kF);
        uint4 I0 = __ldg((const uint4*)(widx + g * 400));
        uint4 I1 = __ldg((const uint4*)(widx + (g + 8) * 400));
#pragma unroll
        for (int i = 0; i < 3; i++) {
            const int p = lane + 32 * i;
            if (p < 16 * kEarlyChunks) {
                const int r = p / kEarlyChunks, c = p - r * kEarlyChunks;
                asm volatile("cp.async.cg.shared.global [%0], [%1], 16;" ::"r"(sb + kOffEarly + warp * (16 * 80) + p * 16),
                             "l"(widx + r * 400 + 16 + c * 16) : "memory");
            }
        }
        float acc[64];
#pragma unroll
        for (int i = 0; i < 64; i++) acc[i] = 0.f;
        const uint32_t tabq = sb + kOffTab + q * 16;
        uint32_t ia = sb + kOffEarly + r0 * 80;
        uint32_t id = 8 * 80;
        const uint32_t lead = (tid & 127) == 0;
        asm volatile("bar.sync 1, %0;" ::"n"(kThreads) : "memory");
        STAMP(1 + (tid >> 7) * 8);
        asm volatile("cp.async.wait_all;" ::: "memory");
        __syncwarp();
        STAMP(2 + (tid >> 7) * 8);
        mbar_wait(sb + kBarTab, 0);
        STAMP(3 + (tid >> 7) * 8);

        uint4 A0[4], A1[4];
        A0[0] = lds128(tabq + I0.x * 64);
        A0[1] = lds128(tabq + I1.x * 64);
        A0[2] = lds128(tabq + I0.y * 64);
        A0[3] = lds128(tabq + I1.y * 64);
        mbar_wait(sb + kBarFull, 0);
        STAMP(4 + (tid >> 7) * 8);

        uint32_t st = 0, ph = 0;
        const uint32_t dbase = kDescLoLbo | ((sb + kOffW) >> 4);
#pragma unroll 1
        for (int j = 0; j < 24; j++) {
            mma_stage(acc, A0, dbase + st * (kStageBytes >> 4));
            mbar_arrive_if(sb + kBarEmpty + (st == 0 ? kNumStages - 1 : st - 1) * 8, lead && j > 0);
            A1[0] = lds128(tabq + I0.z * 64);
            A1[1] = lds128(tabq + I1.z * 64);
            A1[2] = lds128(tabq + I0.w * 64);
            A1[3] = lds128(tabq + I1.w * 64);
            if (j == kEarlyChunks) {
                mbar_wait(sb + kBarIdx, 0);
                ia = sb + kOffIdx + r0 * 400 + (kEarlyChunks + 1) * 16;
                id = 8 * 400;
            }
            I0 = lds128(ia);
            I1 = lds128(ia + id);
            ia += 16;
            mbar_wait(sb + kBarFull + (st + 1) * 8, ph);
            wgmma_wait0();

            mma_stage(acc, A1, dbase + (st + 1) * (kStageBytes >> 4));
            mbar_arrive_if(sb + kBarEmpty + st * 8, lead);
            A0[0] = lds128(tabq + I0.x * 64);
            A0[1] = lds128(tabq + I1.x * 64);
            A0[2] = lds128(tabq + I0.y * 64);
            A0[3] = lds128(tabq + I1.y * 64);
            st += 2;
            if (st == kNumStages) { st = 0; ph ^= 1; }
            mbar_wait(sb + kBarFull + st * 8, ph);
            wgmma_wait0();
        }
        mma_stage(acc, A0, dbase);
        A1[0] = lds128(tabq + I0.z * 64);
        A1[1] = lds128(tabq + I1.z * 64);
        A1[2] = lds128(tabq + I0.w * 64);
        A1[3] = lds128(tabq + I1.w * 64);
        mbar_wait(sb + kBarFull + 8, 0);
        wgmma_wait0();
        mma_stage(acc, A1, dbase + (kStageBytes >> 4));
        mbar_wait(sb + kBarMisc, 0);
        uint4 vb[4], vw[4];
#pragma unroll
        for (int i = 0; i < 4; i++) {
            vb[i] = lds128(sb + kOffB1 + q * 64 + i * 16);
            vw[i] = lds128(sb + kOffW2 + q * 64 + i * 16);
        }
        const float wide = *(const float*)(smem + kOffWide + (r0 + (q & 1) * 8) * 4);
        const float bb2 = *(const float*)(smem + kOffWide + 512);
        wgmma_wait0();
#pragma unroll
        for (int i = 0; i < 64; i++) asm volatile("" : "+f"(acc[i])::"memory");
        STAMP(5 + (tid >> 7) * 8);

        float c0[4] = {0.f, 0.f, 0.f, 0.f}, c1[4] = {0.f, 0.f, 0.f, 0.f};
#pragma unroll
        for (int i = 0; i < 4; i++) {
            const float* a = acc + i * 16;
            mma16816(c0, bias_relu(a[0], a[1], vb[i].x), bias_relu(a[2], a[3], vb[i].x), bias_relu(a[4], a[5], vb[i].y),
                     bias_relu(a[6], a[7], vb[i].y), vw[i].x, vw[i].y);
            mma16816(c1, bias_relu(a[8], a[9], vb[i].z), bias_relu(a[10], a[11], vb[i].z),
                     bias_relu(a[12], a[13], vb[i].w), bias_relu(a[14], a[15], vb[i].w), vw[i].z, vw[i].w);
        }
        const float dsum = (q & 1) ? (c0[2] + c1[2]) : (c0[0] + c1[0]);
        const float deep = bf16r(bf16r(dsum) + bb2);
        const float z = bf16r(wide + deep);
        const float p = 1.0f / (1.0f + __expf(-z));
        if (q < 2) out[cta * kRows + r0 + q * 8] = __float2bfloat16_rn(p);
        STAMP(6 + (tid >> 7) * 8);
    }
}

typedef CUresult (*EncodeTiledFn)(CUtensorMap*, CUtensorMapDataType, cuuint32_t, void*, const cuuint64_t*,
                                  const cuuint64_t*, const cuuint32_t*, const cuuint32_t*, CUtensorMapInterleave,
                                  CUtensorMapSwizzle, CUtensorMapL2promotion, CUtensorMapFloatOOBfill);

}

extern "C" void kernel_launch(void* const* d_in, const int* in_sizes, int n_in, void* d_out, int out_size) {
    (void)in_sizes; (void)n_in; (void)out_size;
    static EncodeTiledFn encode = nullptr;
    if (!encode) {
        void* fn = nullptr;
        cudaDriverEntryPointQueryResult qr;
        cudaGetDriverEntryPoint("cuTensorMapEncodeTiled", &fn, cudaEnableDefault, &qr);
        encode = (EncodeTiledFn)fn;
        cudaFuncSetAttribute(wide_deep_kernel, cudaFuncAttributeMaxDynamicSharedMemorySize, kSmemBytes);
    }
    CUtensorMap map;
    const cuuint64_t dims[5] = {64, 2, 4 * kF, 4, 2};
    const cuuint64_t strides[4] = {256, 2048, 512, 128};
    const cuuint32_t box[5] = {64, 2, 8, 4, 2};
    const cuuint32_t estr[5] = {1, 1, 1, 1, 1};
    encode(&map, CU_TENSOR_MAP_DATA_TYPE_BFLOAT16, 5, d_in[5], dims, strides, box, estr, CU_TENSOR_MAP_INTERLEAVE_NONE,
           CU_TENSOR_MAP_SWIZZLE_128B, CU_TENSOR_MAP_L2_PROMOTION_L2_256B, CU_TENSOR_MAP_FLOAT_OOB_FILL_NONE);
    wide_deep_kernel<<<kGrid, kThreads, kSmemBytes, cudaStreamPerThread>>>(
        map, (const int*)d_in[0], (const __nv_bfloat16*)d_in[1], (const __nv_bfloat16*)d_in[2],
        (const __nv_bfloat16*)d_in[3], (const __nv_bfloat16*)d_in[4], (const __nv_bfloat16*)d_in[5],
        (const __nv_bfloat16*)d_in[6], (const __nv_bfloat16*)d_in[7], (const __nv_bfloat16*)d_in[8],
        (__nv_bfloat16*)d_out);
}
```

```cpp
#include <cuda_runtime.h>
#include <cuda_bf16.h>
#include <cuda.h>
#include <stdint.h>

namespace {

constexpr int kB = 16384, kF = 100, kV = 1000, kNd = 13;
constexpr int kRows = 128;
constexpr int kGrid = kB / kRows;
constexpr int kStageBytes = 16384;
constexpr int kNumStages = 8;
constexpr int kNumK = kF / 2;
constexpr int kThreads = 320;

constexpr uint32_t kSmemBase = 1024;
constexpr int kOffW = 0;
constexpr int kOffB1 = kNumStages * kStageBytes;
constexpr int kOffTab = kOffB1 + 256;
constexpr int kOffIdx = kOffTab + kV * 64;
constexpr int kXwBytes = 4 * kRows * kNd * 2;
constexpr int kOffXw = kOffIdx + kRows * 64;
constexpr int kOffW2 = kOffXw + kXwBytes + 32;
constexpr int kOffWw = kOffW2 + 256;
constexpr int kOffBar = kOffWw + 128;
constexpr int kBarFull = kOffBar, kBarEmpty = kOffBar + 64, kBarMisc = kOffBar + 136;
constexpr int kBarTab = kOffBar + 144;
constexpr int kSmemBytes = kOffBar + 256;

__device__ __forceinline__ uint32_t smem_u32(const void* p) { return (uint32_t)__cvta_generic_to_shared(p); }
__device__ __forceinline__ void mbar_init(uint32_t bar, uint32_t cnt) {
    asm volatile("mbarrier.init.shared::cta.b64 [%0], %1;" ::"r"(bar), "r"(cnt) : "memory");
}
__device__ __forceinline__ void mbar_wait(uint32_t bar, uint32_t parity) {
    asm volatile(
        "{\n.reg .pred p;\n.reg .u32 c;\nmov.u32 c, 0;\n"
        "LAB_WAIT:\n"
        "mbarrier.try_wait.parity.shared::cta.b64 p, [%0], %1;\n"
        "@p bra.uni LAB_DONE;\n"
        "add.u32 c, c, 1;\n"
        "setp.gt.u32 p, c, 4000000;\n"
        "@p trap;\n"
        "bra.uni LAB_WAIT;\n"
        "LAB_DONE:\n}" ::"r"(bar), "r"(parity) : "memory");
}
__device__ __forceinline__ void mbar_wait2(uint32_t bar, uint32_t parity) {
    uint32_t ok;
    asm volatile("{\n.reg .pred p;\nmbarrier.try_wait.parity.shared::cta.b64 p, [%1], %2;\nselp.u32 %0, 1, 0, p;\n}"
                 : "=r"(ok) : "r"(bar), "r"(parity) : "memory");
    if (!ok) mbar_wait(bar, parity);
}
__device__ __forceinline__ void mbar_arrive_if(uint32_t bar, uint32_t pred) {
    asm volatile("{\n.reg .pred p;\nsetp.ne.u32 p, %1, 0;\n@p mbarrier.arrive.shared::cta.b64 _, [%0];\n}" ::"r"(bar),
                 "r"(pred) : "memory");
}
__device__ __forceinline__ void mbar_expect_tx(uint32_t bar, uint32_t bytes) {
    asm volatile("mbarrier.arrive.expect_tx.shared::cta.b64 _, [%0], %1;" ::"r"(bar), "r"(bytes) : "memory");
}
__device__ __forceinline__ void bulk_g2s(uint32_t dst, const void* src, uint32_t bytes, uint32_t bar) {
    asm volatile("cp.async.bulk.shared::cluster.global.mbarrier::complete_tx::bytes [%0], [%1], %2, [%3];" ::"r"(dst),
                 "l"(src), "r"(bytes), "r"(bar) : "memory");
}
__device__ __forceinline__ void bulk_prefetch_l2(const void* src, uint32_t bytes) {
    asm volatile("cp.async.bulk.prefetch.L2.global [%0], %1;" ::"l"(src), "r"(bytes) : "memory");
}
__device__ __forceinline__ void load_stage(uint32_t dst, const CUtensorMap* map, int k, uint32_t bar) {
    asm volatile(
        "cp.async.bulk.tensor.5d.shared::cluster.global.mbarrier::complete_tx::bytes [%0], [%1, {%3, %3, %4, %3, %3}], [%2];" ::"r"(dst),
        "l"(map), "r"(bar), "r"(0), "r"(8 * k) : "memory");
}
__device__ __forceinline__ uint4 tex128(cudaTextureObject_t tex, int x) {
    uint4 v;
    asm volatile("tex.1d.v4.u32.s32 {%0,%1,%2,%3}, [%4, {%5}];" : "=r"(v.x), "=r"(v.y), "=r"(v.z), "=r"(v.w) : "l"(tex), "r"(x));
    return v;
}
__device__ __forceinline__ uint32_t lds32(uint32_t addr) {
    uint32_t v;
    asm volatile("ld.shared.u32 %0, [%1];" : "=r"(v) : "r"(addr));
    return v;
}
__device__ __forceinline__ void cp_async16(uint32_t dst, const void* src) {
    asm volatile("cp.async.cg.shared.global [%0], [%1], 16;" ::"r"(dst), "l"(src) : "memory");
}
__device__ __forceinline__ void cp_async_commit() { asm volatile("cp.async.commit_group;" ::: "memory"); }
template <int N>
__device__ __forceinline__ void cp_async_wait() { asm volatile("cp.async.wait_group %0;" ::"n"(N) : "memory"); }
__device__ __forceinline__ uint4 lds128(uint32_t addr) {
    uint4 v;
    asm volatile("ld.shared.v4.u32 {%0,%1,%2,%3}, [%4];" : "=r"(v.x), "=r"(v.y), "=r"(v.z), "=r"(v.w) : "r"(addr));
    return v;
}
__device__ __forceinline__ void wgmma_fence() { asm volatile("wgmma.fence.sync.aligned;" ::: "memory"); }
__device__ __forceinline__ void wgmma_commit() { asm volatile("wgmma.commit_group.sync.aligned;" ::: "memory"); }
template <int N>
__device__ __forceinline__ void wgmma_wait() { asm volatile("wgmma.wait_group.sync.aligned %0;" ::"n"(N) : "memory"); }
__device__ __forceinline__ bool elect_one() {
    uint32_t p;
    asm volatile("{\n.reg .pred p;\nelect.sync _|p, 0xffffffff;\nselp.u32 %0, 1, 0, p;\n}" : "=r"(p));
    return p;
}

constexpr uint32_t kDescHi = (1u << 30) | (4096 >> 4);
constexpr uint32_t kDescLoLbo = (8192 >> 4) << 16;

template <uint32_t DHI = kDescHi>
__device__ __forceinline__ void wgmma_rs(float (&d)[64], uint32_t a0, uint32_t a1, uint32_t a2, uint32_t a3,
                                         uint32_t dlo, uint32_t accum = 1) {
    asm volatile(
        "{\n.reg .pred p;\n.reg .b64 db;\nsetp.ne.b32 p, %70, 0;\nmov.b64 db, {%68, %69};\n"
        "wgmma.mma_async.sync.aligned.m64n128k16.f32.bf16.bf16 "
        "{%0,%1,%2,%3,%4,%5,%6,%7,%8,%9,%10,%11,%12,%13,%14,%15,"
        "%16,%17,%18,%19,%20,%21,%22,%23,%24,%25,%26,%27,%28,%29,%30,%31,"
        "%32,%33,%34,%35,%36,%37,%38,%39,%40,%41,%42,%43,%44,%45,%46,%47,"
        "%48,%49,%50,%51,%52,%53,%54,%55,%56,%57,%58,%59,%60,%61,%62,%63},"
        "{%64,%65,%66,%67}, db, p, 1, 1, 1;\n}"
        : "+f"(d[0]), "+f"(d[1]), "+f"(d[2]), "+f"(d[3]), "+f"(d[4]), "+f"(d[5]), "+f"(d[6]), "+f"(d[7]),
          "+f"(d[8]), "+f"(d[9]), "+f"(d[10]), "+f"(d[11]), "+f"(d[12]), "+f"(d[13]), "+f"(d[14]), "+f"(d[15]),
          "+f"(d[16]), "+f"(d[17]), "+f"(d[18]), "+f"(d[19]), "+f"(d[20]), "+f"(d[21]), "+f"(d[22]), "+f"(d[23]),
          "+f"(d[24]), "+f"(d[25]), "+f"(d[26]), "+f"(d[27]), "+f"(d[28]), "+f"(d[29]), "+f"(d[30]), "+f"(d[31]),
          "+f"(d[32]), "+f"(d[33]), "+f"(d[34]), "+f"(d[35]), "+f"(d[36]), "+f"(d[37]), "+f"(d[38]), "+f"(d[39]),
          "+f"(d[40]), "+f"(d[41]), "+f"(d[42]), "+f"(d[43]), "+f"(d[44]), "+f"(d[45]), "+f"(d[46]), "+f"(d[47]),
          "+f"(d[48]), "+f"(d[49]), "+f"(d[50]), "+f"(d[51]), "+f"(d[52]), "+f"(d[53]), "+f"(d[54]), "+f"(d[55]),
          "+f"(d[56]), "+f"(d[57]), "+f"(d[58]), "+f"(d[59]), "+f"(d[60]), "+f"(d[61]), "+f"(d[62]), "+f"(d[63])
        : "r"(a0), "r"(a1), "r"(a2), "r"(a3), "r"(dlo), "n"(DHI), "r"(accum));
}
__device__ __forceinline__ void mma_stage(float (&acc)[64], const uint4 (&A)[4], uint32_t dlo) {
    wgmma_fence();
    wgmma_rs(acc, A[0].x, A[1].x, A[0].z, A[1].z, dlo);
    wgmma_rs(acc, A[0].y, A[1].y, A[0].w, A[1].w, dlo + (2048 >> 4));
    wgmma_rs(acc, A[2].x, A[3].x, A[2].z, A[3].z, dlo + (1024 >> 4));
    wgmma_rs(acc, A[2].y, A[3].y, A[2].w, A[3].w, dlo + (3072 >> 4));
    wgmma_commit();
}
__device__ __forceinline__ void gather(uint4 (&A)[4], uint32_t a0, uint32_t a1, uint32_t b0, uint32_t b1, uint32_t tab) {
    A[0] = lds128(tab + a0 * 64);
    A[1] = lds128(tab + a1 * 64);
    A[2] = lds128(tab + b0 * 64);
    A[3] = lds128(tab + b1 * 64);
}
__device__ __forceinline__ void mma16816(float (&c)[4], uint32_t a0, uint32_t a1, uint32_t a2, uint32_t a3, uint32_t b0,
                                         uint32_t b1) {
    asm volatile("mma.sync.aligned.m16n8k16.row.col.f32.bf16.bf16.f32 {%0,%1,%2,%3}, {%4,%5,%6,%7}, {%8,%9}, {%0,%1,%2,%3};"
                 : "+f"(c[0]), "+f"(c[1]), "+f"(c[2]), "+f"(c[3])
                 : "r"(a0), "r"(a1), "r"(a2), "r"(a3), "r"(b0), "r"(b1));
}
__device__ __forceinline__ uint32_t pack_relu(float lo, float hi) {
    uint32_t h;
    asm("cvt.rn.relu.bf16x2.f32 %0, %1, %2;" : "=r"(h) : "f"(hi), "f"(lo));
    return h;
}
__device__ __forceinline__ uint32_t pack_bf16(float lo, float hi) {
    uint32_t h;
    asm("cvt.rn.bf16x2.f32 %0, %1, %2;" : "=r"(h) : "f"(hi), "f"(lo));
    return h;
}
__device__ __forceinline__ uint4 ldsm4(uint32_t addr) {
    uint4 v;
    asm volatile("ldmatrix.sync.aligned.m8n8.x4.shared.b16 {%0,%1,%2,%3}, [%4];"
                 : "=r"(v.x), "=r"(v.y), "=r"(v.z), "=r"(v.w) : "r"(addr));
    return v;
}
__device__ __forceinline__ float bf16lo(uint32_t w) { return __uint_as_float(w << 16); }
__device__ __forceinline__ float bf16hi(uint32_t w) { return __uint_as_float(w & 0xFFFF0000u); }

__global__ void __launch_bounds__(kThreads, 1)
wide_deep_kernel(const int* __restrict__ idx, const __nv_bfloat16* __restrict__ table,
                 const __nv_bfloat16* __restrict__ b1, const __nv_bfloat16* __restrict__ W1,
                 cudaTextureObject_t idx_tex, __nv_bfloat16* __restrict__ out,
                 const __nv_bfloat16* __restrict__ x_wide, const __nv_bfloat16* __restrict__ w_wide,
                 const __nv_bfloat16* __restrict__ b_wide, const __nv_bfloat16* __restrict__ b2,
                 const __nv_bfloat16* __restrict__ W2,
                 const __grid_constant__ CUtensorMap map0) {
    extern __shared__ __align__(1024) uint8_t smem[];
    constexpr uint32_t sb = kSmemBase;
    const int tid = threadIdx.x, lane = tid & 31;
    const int cta = blockIdx.x;
    uint32_t t0 = 0;
    if (__any_sync(0xffffffffu, tid >= 288)) {
        if (elect_one()) {
            mbar_init(sb + kBarTab, 1);
            mbar_init(sb + kBarMisc, 33);
            mbar_expect_tx(sb + kBarTab, kV * 64 + 256);
        }
        __syncwarp();
        uint32_t o, rest;
        asm volatile("{\n.reg .u32 t;\nmov.u32 t, %%smid;\nand.b32 t, t, 127;\nmad.lo.u32 %0, t, 496, 16;\nsub.u32 %1, %2, %0;\n}"
                     : "=r"(o), "=r"(rest) : "n"(kV * 64));
        mbar_wait(sb + kBarTab, 1);
        if (elect_one()) {
            bulk_g2s(sb + kOffTab + o, (const uint8_t*)table + o, rest, sb + kBarTab);
            bulk_g2s(sb + kOffB1, b1, 256, sb + kBarTab);
            bulk_g2s(sb + kOffTab, table, o, sb + kBarTab);
        }
        __syncwarp();
        asm volatile("bar.arrive 2, 64;" ::: "memory");
        asm volatile("mov.u32 %0, %%clock;" : "=r"(t0));
    }
    const int warp = __shfl_sync(0xffffffffu, tid >> 5, 0);

    const int blk = cta & 31, cls = cta >> 5, c0 = (4 - cls) & 3;

    if (warp == 9) {
        if (smem_u32(smem) != kSmemBase) __trap();
        const uint32_t k = lane - (cls & 1);
        const __nv_bfloat16* sp = lane < 16 ? w_wide + min(k, (uint32_t)(kNd - 1)) : (lane == 16 ? b_wide : b2);
        const uint8_t* pf = (const uint8_t*)W1 + 10 * kStageBytes + cta * 5120;
        const uint8_t* xs = (const uint8_t*)x_wide + blk * kXwBytes;
        asm volatile("" : "+l"(sp), "+l"(pf), "+l"(xs));
        asm volatile("bar.arrive 1, %0;" ::"n"(kThreads) : "memory");
        uint32_t wz = 0;
        {
            uint32_t n = 0, t;
            do {
                asm volatile("mov.u32 %0, %%clock;" : "=r"(t));
            } while (t - t0 < 900 && ++n < 500);
            float w[4] = {0.f, 0.f, 0.f, 0.f};
            mma16816(w, n >> 10, 0, 0, 0, n, 0);
            wz = __float_as_uint(w[0]);
        }
        asm volatile("bar.sync 4, 64;" ::: "memory");
        mbar_wait(sb + kBarEmpty + wz, 0);
        if (elect_one()) {
            bulk_prefetch_l2(pf, 5120);
            mbar_expect_tx(sb + kBarMisc, kXwBytes + 256);
            bulk_g2s(sb + kOffW2, W2, 256, sb + kBarMisc);
            bulk_g2s(sb + kOffXw, xs, kXwBytes, sb + kBarMisc);
        }
        uint16_t sv;
        asm volatile("ld.volatile.global.u16 %0, [%1];" : "=h"(sv) : "l"(sp) : "memory");
        if (lane < 16 && k >= kNd) sv = 0;
        ((uint16_t*)(smem + kOffWw))[lane] = sv;
        mbar_arrive_if(sb + kBarMisc, 1);
    } else if (warp == 8) {
        if (elect_one()) {
            mbar_init(sb + kBarFull, 1);
            mbar_init(sb + kBarFull + 8, 1);
            mbar_expect_tx(sb + kBarFull, kStageBytes);
            mbar_expect_tx(sb + kBarFull + 8, kStageBytes);
        }
        __syncwarp();
        asm volatile("bar.sync 2, 64;" ::: "memory");
        if (elect_one()) {
            load_stage(sb + kOffW, &map0, 2 * c0, sb + kBarFull);
            load_stage(sb + kOffW + kStageBytes, &map0, 2 * c0 + 1, sb + kBarFull + 8);
            bulk_prefetch_l2((const uint8_t*)W1 + 8 * kStageBytes + cta * 256, 256);
#pragma unroll
            for (int s = 0; s < kNumStages; s++) {
                if (s >= 2) mbar_init(sb + kBarFull + s * 8, 1);
                mbar_init(sb + kBarEmpty + s * 8, 2);
            }
        }
        __syncwarp();
        asm volatile("bar.arrive 1, %0;" ::"n"(kThreads) : "memory");
        asm volatile("bar.arrive 4, 64;" ::: "memory");
        mbar_wait(sb + kBarFull, 0);
        if (elect_one()) {
#pragma unroll
            for (int s = 2; s < kNumStages; s++) {
                mbar_expect_tx(sb + kBarFull + s * 8, kStageBytes);
                load_stage(sb + kOffW + s * kStageBytes, &map0, 2 * c0 + s, sb + kBarFull + s * 8);
            }
        }
        __syncwarp();
        int st = 0, kw = 2 * c0 + kNumStages;
        uint32_t ph = 0;
#pragma unroll 1
        for (int k = kNumStages; k < kNumK; k++) {
            mbar_wait(sb + kBarEmpty + st * 8, ph);
            if (elect_one()) {
                const uint32_t bar = sb + kBarFull + st * 8;
                mbar_expect_tx(bar, kStageBytes);
                load_stage(sb + kOffW + st * kStageBytes, &map0, kw, bar);
            }
            __syncwarp();
            if (++st == kNumStages) { st = 0; ph ^= 1; }
            if (++kw == kNumK) kw = 0;
        }
    } else {
        const int g = lane >> 2, q = lane & 3;
        const int r0 = warp * 16 + g;
        const uint32_t ia0 = sb + kOffIdx + warp * 1024 + (g >> 1) * 256 + (g & 1) * 64;
        {
            const uint8_t* isrc = (const uint8_t*)idx + (uint32_t)(((blk * kRows + r0) * 4 + cls) * (kF * 4) + (c0 + q) * 16);
            const uint32_t idst = ia0 + (q ^ (g >> 1)) * 16;
            cp_async16(idst, isrc);
            cp_async16(idst + 128, isrc + 8 * 4 * kF * 4);
            cp_async_commit();
        }
        const uint32_t tab = sb + kOffTab + q * 16;
        const int tx0 = ((blk * kRows + r0) * 4 + cls) * (kF / 4);
        const uint32_t lead = (tid & 127) == 0;
        asm volatile("bar.sync 1, %0;" ::"n"(kThreads) : "memory");
        mbar_wait(sb + kBarEmpty + 8, 1);
        __nv_bfloat16* outp = out + (blk * kRows + r0 + (q & 1) * 8) * 4 + cls;
        asm volatile("" : "+l"(outp));
        float acc[64];
#pragma unroll
        for (int i = 0; i < 64; i++) asm volatile("" : "=f"(acc[i]));
        uint32_t e0 = q == 0 ? 0x3F80u : 0u;
        cp_async_wait<0>();
        __syncwarp();
        uint4 P0[4], P1[4];
#pragma unroll
        for (int i = 0; i < 4; i++) {
            P0[i] = lds128(ia0 + (i ^ (g >> 1)) * 16);
            P1[i] = lds128(ia0 + (i ^ (g >> 1)) * 16 + 128);
        }
        const uint32_t dbase = kDescLoLbo | ((sb + kOffW) >> 4);
        uint32_t ad[4] = {tab + P0[0].x * 64, tab + P1[0].x * 64, tab + P0[0].y * 64, tab + P1[0].y * 64};
        asm volatile("" : "+r"(ad[0]), "+r"(ad[1]), "+r"(ad[2]), "+r"(ad[3]), "+r"(e0));
        mbar_wait(sb + kBarTab, 0);

        if (warp >= 4) mbar_wait(sb + kBarFull, 0);
        wgmma_fence();
        wgmma_rs<1>(acc, e0, e0, 0, 0, (1u << 16) | ((sb + kOffB1) >> 4), 0);
        wgmma_commit();
        uint4 A[2][4];
        int cn = c0 + 4;
        A[0][0] = lds128(ad[0]), A[0][1] = lds128(ad[1]), A[0][2] = lds128(ad[2]), A[0][3] = lds128(ad[3]);
        mbar_wait2(sb + kBarFull, 0);

        uint32_t ph = 0, rel = 0;
#pragma unroll 1
        for (int jj = 0; jj < 6; jj++) {
#pragma unroll
            for (int s = 0; s < kNumStages; s++) {
                wgmma_wait<0>();
                mma_stage(acc, A[s & 1], dbase + s * (kStageBytes >> 4));
                mbar_arrive_if(sb + kBarEmpty + ((s + kNumStages - 1) % kNumStages) * 8, s > 0 ? lead : rel);
                if ((s & 1) == 0) {
                    gather(A[1], P0[s >> 1].z, P1[s >> 1].z, P0[s >> 1].w, P1[s >> 1].w, tab);
                } else {
                    const int i = ((s + 1) >> 1) % 4;
                    gather(A[0], P0[i].x, P1[i].x, P0[i].y, P1[i].y, tab);
                }
                if ((s & 1) == 0) {
                    P0[s >> 1] = tex128(idx_tex, tx0 + cn);
                } else {
                    P1[s >> 1] = tex128(idx_tex, tx0 + cn + 8 * kF);
                    cn = cn == kF / 4 - 1 ? 0 : cn + 1;
                }
                mbar_wait2(sb + kBarFull + ((s + 1) % kNumStages) * 8, s + 1 == kNumStages ? ph ^ 1 : ph);
            }
            ph ^= 1;
            rel = lead;
        }
        wgmma_wait<0>();
        mma_stage(acc, A[0], dbase);
        mbar_wait(sb + kBarMisc, 0);
        gather(A[1], P0[0].z, P1[0].z, P0[0].w, P1[0].w, tab);
        mbar_wait2(sb + kBarFull + 8, 0);
        wgmma_wait<0>();
        mma_stage(acc, A[1], dbase + (kStageBytes >> 4));
        mbar_wait(sb + kBarMisc, 0);
        uint32_t xa[4];
        {
            const uint32_t x0 = sb + kOffXw + (r0 * 4 + cls) * 26 - (cls & 1) * 2 + q * 4, x1 = x0 + 32 * 26;
            const uint32_t m0 = (q == 0 && (cls & 1)) ? 0xFFFF0000u : 0xFFFFFFFFu;
            const uint32_t m1 = q == 3 ? 0u : ((q == 2 && !(cls & 1)) ? 0xFFFFu : 0xFFFFFFFFu);
            xa[0] = lds32(x0) & m0;
            xa[1] = lds32(x1) & m0;
            xa[2] = lds32(x0 + 16) & m1;
            xa[3] = lds32(x1 + 16) & m1;
        }
        uint32_t vw[16];
#pragma unroll
        for (int i = 0; i < 4; i++) {
            const uint4 v = ldsm4(sb + kOffW2 + (4 * i + (lane >> 3) + ((lane & 7) == 2 ? 0 : (lane & 7))) * 16);
            vw[4 * i] = v.x, vw[4 * i + 1] = v.y, vw[4 * i + 2] = v.z, vw[4 * i + 3] = v.w;
        }
        const uint32_t wb0 = lds32(sb + kOffWw + q * 4), wb1 = lds32(sb + kOffWw + 16 + q * 4);
        const uint32_t bias2 = lds32(sb + kOffWw + 32);
        float bias = bf16lo(bias2) + bf16hi(bias2);
        asm volatile("" : "+r"(xa[0]), "+r"(xa[1]), "+r"(xa[2]), "+r"(xa[3]), "+f"(bias));
        mbar_wait(sb + kBarMisc, 0);
        wgmma_wait<0>();
#pragma unroll
        for (int i = 0; i < 64; i++) asm volatile("" : "+f"(acc[i])::"memory");

        float c[4][4] = {{0.f, 0.f, 0.f, 0.f}, {0.f, 0.f, 0.f, 0.f}, {0.f, 0.f, 0.f, 0.f}, {bias, bias, bias, bias}};
        mma16816(c[3], xa[0], xa[1], xa[2], xa[3], wb0, wb1);
#pragma unroll
        for (int i = 0; i < 4; i++) {
            const float* a = acc + i * 16;
            mma16816(c[(2 * i) & 3], pack_relu(a[0], a[1]), pack_relu(a[2], a[3]), pack_relu(a[4], a[5]),
                     pack_relu(a[6], a[7]), vw[4 * i], vw[4 * i + 1]);
            mma16816(c[(2 * i + 1) & 3], pack_relu(a[8], a[9]), pack_relu(a[10], a[11]), pack_relu(a[12], a[13]),
                     pack_relu(a[14], a[15]), vw[4 * i + 2], vw[4 * i + 3]);
        }
        const float z = (q & 1) ? (c[0][2] + c[1][2]) + (c[2][2] + c[3][2]) : (c[0][0] + c[1][0]) + (c[2][0] + c[3][0]);
        float e, p;
        asm("ex2.approx.ftz.f32 %0, %1;" : "=f"(e) : "f"(z * -1.4426950408889634f));
        asm("rcp.approx.ftz.f32 %0, %1;" : "=f"(p) : "f"(1.0f + e));
        if (q < 2) asm volatile("st.global.u16 [%0], %1;" ::"l"(outp), "h"((uint16_t)pack_bf16(p, p)) : "memory");
    }
}

typedef CUresult (*EncodeTiledFn)(CUtensorMap*, CUtensorMapDataType, cuuint32_t, void*, const cuuint64_t*,
                                  const cuuint64_t*, const cuuint32_t*, const cuuint32_t*, CUtensorMapInterleave,
                                  CUtensorMapSwizzle, CUtensorMapL2promotion, CUtensorMapFloatOOBfill);

}

extern "C" void kernel_launch(void* const* d_in, const int* in_sizes, int n_in, void* d_out, int out_size) {
    (void)in_sizes; (void)n_in; (void)out_size;
    static EncodeTiledFn encode = nullptr;
    if (!encode) {
        void* fn = nullptr;
        cudaDriverEntryPointQueryResult qr;
        cudaGetDriverEntryPoint("cuTensorMapEncodeTiled", &fn, cudaEnableDefault, &qr);
        encode = (EncodeTiledFn)fn;
        cudaFuncSetAttribute(wide_deep_kernel, cudaFuncAttributeMaxDynamicSharedMemorySize, kSmemBytes);
    }
    CUtensorMap map;
    {
        const cuuint64_t dims[5] = {64, 2, 4 * kF, 4, 2};
        const cuuint64_t strides[4] = {256, 2048, 512, 128};
        const cuuint32_t box[5] = {64, 2, 8, 4, 2};
        const cuuint32_t estr[5] = {1, 1, 1, 1, 1};
        encode(&map, CU_TENSOR_MAP_DATA_TYPE_BFLOAT16, 5, d_in[5], dims, strides, box, estr, CU_TENSOR_MAP_INTERLEAVE_NONE,
               CU_TENSOR_MAP_SWIZZLE_128B, CU_TENSOR_MAP_L2_PROMOTION_L2_256B, CU_TENSOR_MAP_FLOAT_OOB_FILL_NONE);
    }
    static cudaTextureObject_t tex = 0;
    static void* tex_ptr = nullptr;
    if (tex_ptr != d_in[0]) {
        cudaResourceDesc rd = {};
        rd.resType = cudaResourceTypeLinear;
        rd.res.linear.devPtr = d_in[0];
        rd.res.linear.desc = cudaCreateChannelDesc(32, 32, 32, 32, cudaChannelFormatKindUnsigned);
        rd.res.linear.sizeInBytes = (size_t)kB * kF * 4;
        cudaTextureDesc td = {};
        td.readMode = cudaReadModeElementType;
        cudaCreateTextureObject(&tex, &rd, &td, nullptr);
        tex_ptr = d_in[0];
    }
    wide_deep_kernel<<<kGrid, kThreads, kSmemBytes, cudaStreamPerThread>>>(
        (const int*)d_in[0], (const __nv_bfloat16*)d_in[1], (const __nv_bfloat16*)d_in[6],
        (const __nv_bfloat16*)d_in[5], tex, (__nv_bfloat16*)d_out,
        (const __nv_bfloat16*)d_in[2], (const __nv_bfloat16*)d_in[3], (const __nv_bfloat16*)d_in[4],
        (const __nv_bfloat16*)d_in[8],
        (const __nv_bfloat16*)d_in[7], map);
}
```
